```python
import torch

def _softmax(x, axis=-1):
    return torch.softmax(x, dim=axis)
def _gelu(x):
    return torch.nn.functional.gelu(x, approximate="tanh")
def _silu(x):
    return torch.nn.functional.silu(x)
def _sigmoid(x):
    return torch.sigmoid(x)
def _layernorm(x, axis=-1, eps=1e-5):
    m = x.mean(dim=axis, keepdim=True)
    v = x.var(dim=axis, keepdim=True, unbiased=False)
    return (x - m) / torch.sqrt(v + eps)
def _scatter_add(tgt, idx, src, axis=0):
    return tgt.clone().index_add_(axis, idx, src)
def _segment_sum(src, seg, n):
    out = torch.zeros((n,) + src.shape[1:], dtype=src.dtype)
    return out.index_add_(0, seg, src)
def _pad(x, pw):
    flat = tuple(v for pair in reversed(pw) for v in pair)
    return torch.nn.functional.pad(x, flat)

kernel_name = 'parallel_sum__linear_attn_block__geglu_ffn__prompt'

def setup_inputs():

    _w = (lambda a: (lambda t: t.to(torch.bfloat16) if t.is_floating_point() else t)(torch.as_tensor(a)))
    def _A_setup():
        B, S, D = 1, 2048, 448
        return {
            "x": _w((lambda *s: torch.randn(*s, dtype=torch.bfloat16) * 0.05)(B, S, D)),
            "wqkv": _w((lambda *s: torch.randn(*s, dtype=torch.bfloat16) * 0.4)(D, 3 * D)),
            "wo": _w((lambda *s: torch.randn(*s, dtype=torch.bfloat16) * 0.2)(D, D)),
        }
    _A_in = _A_setup()

    def _B_setup():
        B, S, D, F = 1, 2048, 448, 1792
        return {
            "x": _w((lambda *s: torch.randn(*s, dtype=torch.bfloat16) * 0.05)(B, S, D)),
            "w_gate": _w((lambda *s: torch.randn(*s, dtype=torch.bfloat16) * 0.05)(D, F)),
            "w_up": _w((lambda *s: torch.randn(*s, dtype=torch.bfloat16) * 0.05)(D, F)),
            "w_down": _w((lambda *s: torch.randn(*s, dtype=torch.bfloat16) * 0.05)(F, D)),
        }
    _B_in = _B_setup()

    return {
        "A_x": _A_in["x"],
        "A_wqkv": _A_in["wqkv"],
        "A_wo": _A_in["wo"],
        "B_x": _B_in["x"],
        "B_w_gate": _B_in["w_gate"],
        "B_w_up": _B_in["w_up"],
        "B_w_down": _B_in["w_down"],
    }

def reference(A_x, A_wqkv, A_wo, B_x, B_w_gate, B_w_up, B_w_down):
    def _A_ref(x, wqkv, wo):
        B, S, D = x.shape
        H = 16; Dh = D // H
        qkv = (lambda x, *d: x.permute(*d))((x @ wqkv).reshape(B, S, 3, H, Dh), 2, 0, 3, 1, 4)
        q, k, v = qkv[0], qkv[1], qkv[2]
        phi = lambda t: torch.where(t > 0, t + 1, torch.exp(t)) + 1e-6
        pq, pk = phi(q), phi(k)
        kv = torch.einsum("bhsd,bhse->bhde", pk, v)
        z = torch.einsum("bhsd->bhd", pk)
        num = torch.einsum("bhqd,bhde->bhqe", pq, kv)
        den = torch.einsum("bhqd,bhd->bhq", pq, z)[..., None] + 1e-6
        o = num / den
        return (lambda x, *d: x.permute(*d))(o, 0, 2, 1, 3).reshape(B, S, D) @ wo

    def _B_ref(x, w_gate, w_up, w_down):
        return (_gelu(x @ w_gate) * (x @ w_up)) @ w_down

    x = A_x
    xn = _layernorm(x, axis=-1)
    return x + _A_ref(xn, A_wqkv, A_wo) + _B_ref(xn, B_w_gate, B_w_up, B_w_down)
```

```cpp
#include <cuda_runtime.h>
#include <cuda.h>
#include <cuda_bf16.h>
#include <stdint.h>

__device__ __forceinline__ void wgmma_rs_n64(float (&d)[32], uint32_t a0, uint32_t a1, uint32_t a2, uint32_t a3, uint64_t db, int sd) {
  asm volatile("{\n.reg .pred p;\nsetp.ne.b32 p, %37, 0;\n"
    "wgmma.mma_async.sync.aligned.m64n64k16.f32.bf16.bf16 {%0, %1, %2, %3, %4, %5, %6, %7, %8, %9, %10, %11, %12, %13, %14, %15, %16, %17, %18, %19, %20, %21, %22, %23, %24, %25, %26, %27, %28, %29, %30, %31}, {%32,%33,%34,%35}, %36, p, 1, 1, 1;\n}\n"
    : "+f"(d[0]), "+f"(d[1]), "+f"(d[2]), "+f"(d[3]), "+f"(d[4]), "+f"(d[5]), "+f"(d[6]), "+f"(d[7]), "+f"(d[8]), "+f"(d[9]), "+f"(d[10]), "+f"(d[11]), "+f"(d[12]), "+f"(d[13]), "+f"(d[14]), "+f"(d[15]), "+f"(d[16]), "+f"(d[17]), "+f"(d[18]), "+f"(d[19]), "+f"(d[20]), "+f"(d[21]), "+f"(d[22]), "+f"(d[23]), "+f"(d[24]), "+f"(d[25]), "+f"(d[26]), "+f"(d[27]), "+f"(d[28]), "+f"(d[29]), "+f"(d[30]), "+f"(d[31]) : "r"(a0), "r"(a1), "r"(a2), "r"(a3), "l"(db), "r"(sd));
}
__device__ __forceinline__ void wgmma_rs_n56(float (&d)[28], uint32_t a0, uint32_t a1, uint32_t a2, uint32_t a3, uint64_t db, int sd) {
  asm volatile("{\n.reg .pred p;\nsetp.ne.b32 p, %33, 0;\n"
    "wgmma.mma_async.sync.aligned.m64n56k16.f32.bf16.bf16 {%0, %1, %2, %3, %4, %5, %6, %7, %8, %9, %10, %11, %12, %13, %14, %15, %16, %17, %18, %19, %20, %21, %22, %23, %24, %25, %26, %27}, {%28,%29,%30,%31}, %32, p, 1, 1, 1;\n}\n"
    : "+f"(d[0]), "+f"(d[1]), "+f"(d[2]), "+f"(d[3]), "+f"(d[4]), "+f"(d[5]), "+f"(d[6]), "+f"(d[7]), "+f"(d[8]), "+f"(d[9]), "+f"(d[10]), "+f"(d[11]), "+f"(d[12]), "+f"(d[13]), "+f"(d[14]), "+f"(d[15]), "+f"(d[16]), "+f"(d[17]), "+f"(d[18]), "+f"(d[19]), "+f"(d[20]), "+f"(d[21]), "+f"(d[22]), "+f"(d[23]), "+f"(d[24]), "+f"(d[25]), "+f"(d[26]), "+f"(d[27]) : "r"(a0), "r"(a1), "r"(a2), "r"(a3), "l"(db), "r"(sd));
}
__device__ __forceinline__ void wgmma_ss_n56_ta1tb1(float (&d)[28], uint64_t da, uint64_t db, int sd) {
  asm volatile("{\n.reg .pred p;\nsetp.ne.b32 p, %30, 0;\n"
    "wgmma.mma_async.sync.aligned.m64n56k16.f32.bf16.bf16 {%0, %1, %2, %3, %4, %5, %6, %7, %8, %9, %10, %11, %12, %13, %14, %15, %16, %17, %18, %19, %20, %21, %22, %23, %24, %25, %26, %27}, %28, %29, p, 1, 1, 1, 1;\n}\n"
    : "+f"(d[0]), "+f"(d[1]), "+f"(d[2]), "+f"(d[3]), "+f"(d[4]), "+f"(d[5]), "+f"(d[6]), "+f"(d[7]), "+f"(d[8]), "+f"(d[9]), "+f"(d[10]), "+f"(d[11]), "+f"(d[12]), "+f"(d[13]), "+f"(d[14]), "+f"(d[15]), "+f"(d[16]), "+f"(d[17]), "+f"(d[18]), "+f"(d[19]), "+f"(d[20]), "+f"(d[21]), "+f"(d[22]), "+f"(d[23]), "+f"(d[24]), "+f"(d[25]), "+f"(d[26]), "+f"(d[27]) : "l"(da), "l"(db), "r"(sd));
}

namespace {

constexpr uint32_t XW_BYTES = 57344, SLOT = 14336;
constexpr uint32_t OFF_RING = 2 * XW_BYTES;
constexpr uint32_t OFF_BAR = OFF_RING + 8 * SLOT;
constexpr uint32_t SMEM_BYTES = OFF_BAR + 1024;
constexpr uint32_t XO_PARK = 0, XO_STG = 16384, XO_KV = 32768, XO_G0 = 40960, XO_KVD = 49152;
constexpr int B_FULL = 0, B_EMPTY = 8, B_LAND = 16, B_PEER = 23, B_KV = 24, B_KVD = 26, B_STG = 27, B_CS = 34, B_CH = 35;
constexpr uint32_t OFF_CS = OFF_BAR + 512;
constexpr uint32_t SB0 = 1024, DRING = (SB0 + OFF_RING) >> 4;
constexpr int I_G2 = 40;
#define XL_AT 4
#define STAG -1
#define PF0 1
#define CS_AT 5
#define ETMA 0
#define KV_AT 4
#define DRED 0
#define LS 0
#define G6 0
#define SQ_AT 0
#define GA 27
#define GB 32
#define GC 34
#define GD 36
#define REL 1
#define FENCE_ASYNC_GLOBAL asm volatile("fence.proxy.async.global;" ::: "memory")
#define EPF 2
#define NCP 1

struct __align__(64) Params {
  const __nv_bfloat16 *x, *wu, *wg, *wqkv, *wd, *wo;
  __nv_bfloat16* out;
  CUtensorMap tmX, tmU64, tmG64, tmG, tmU, tmQ, tmG32, tmU32, tmWd96, tmWd32, tmWo, tmOut;
};

__device__ __align__(128) float g_kv[2][8][2048];
__device__ __align__(128) float g_cs[2][8][128];
__device__ unsigned g_cnt[2][32];
__device__ unsigned g_epoch[128];
#define TLREC(r, k)
#define TLREG(r, k)

__device__ __forceinline__ uint32_t smem_u32(const void* p) { return (uint32_t)__cvta_generic_to_shared(p); }
__device__ __forceinline__ void die() { asm volatile("st.global.u32 [%0], %1;" ::"l"(0ull), "r"(0) : "memory"); }
__device__ __forceinline__ void mbar_init(uint32_t b, int c) { asm volatile("mbarrier.init.shared::cta.b64 [%0], %1;" ::"r"(b), "r"(c) : "memory"); }
__device__ __forceinline__ void mbar_expect(uint32_t b, uint32_t bytes) { asm volatile("mbarrier.arrive.expect_tx.shared::cta.b64 _, [%0], %1;" ::"r"(b), "r"(bytes) : "memory"); }
__device__ __forceinline__ void mbar_arrive(uint32_t b) { asm volatile("mbarrier.arrive.shared::cta.b64 _, [%0];" ::"r"(b) : "memory"); }
__device__ __forceinline__ void mbar_wait(uint32_t b, uint32_t ph) {
  asm volatile("{\n.reg .pred p;\n.reg .u32 n;\n.reg .u64 z;\nmov.u32 n, 0;\nLW:\n"
               "mbarrier.try_wait.parity.shared::cta.b64 p, [%0], %1;\n@p bra LD;\n"
               "add.u32 n, n, 1;\nsetp.lt.u32 p, n, 0x200000;\n@p bra LW;\n"
               "mov.u64 z, 0;\nst.global.u32 [z], n;\nLD:\n}" ::"r"(b), "r"(ph) : "memory");
}
__device__ __forceinline__ uint32_t mbar_probe(uint32_t b, uint32_t ph) {
  uint32_t ok;
  asm volatile("{\n.reg .pred p;\nmbarrier.test_wait.parity.shared::cta.b64 p, [%1], %2;\nselp.u32 %0, 1, 0, p;\n}" : "=r"(ok) : "r"(b), "r"(ph) : "memory");
  return ok;
}
__device__ __forceinline__ void mbar_ensure(uint32_t ok, uint32_t b, uint32_t ph) {
  asm volatile("{\n.reg .pred p;\n.reg .u32 n;\n.reg .u64 z;\nsetp.ne.u32 p, %2, 0;\n@p bra LD;\nmov.u32 n, 0;\nLW:\n"
               "mbarrier.try_wait.parity.shared::cta.b64 p, [%0], %1;\n@p bra LD;\n"
               "add.u32 n, n, 1;\nsetp.lt.u32 p, n, 0x200000;\n@p bra LW;\n"
               "mov.u64 z, 0;\nst.global.u32 [z], n;\nLD:\n}" ::"r"(b), "r"(ph), "r"(ok) : "memory");
}
#define WG_FENCE asm volatile("wgmma.fence.sync.aligned;" ::: "memory")
#define WG_COMMIT asm volatile("wgmma.commit_group.sync.aligned;" ::: "memory")
#define WG_WAIT(n) asm volatile("wgmma.wait_group.sync.aligned " #n ";" ::: "memory")
#define FENCE_ASYNC_SMEM asm volatile("fence.proxy.async.shared::cta;" ::: "memory")
__device__ __forceinline__ void bar_sync(int id, int n) { asm volatile("bar.sync %0, %1;" ::"r"(id), "r"(n) : "memory"); }
template <int N> __device__ __forceinline__ void fence_regs(float (&d)[N]) {
#pragma unroll
  for (int i = 0; i < N; i++) asm volatile("" : "+f"(d[i])::"memory");
}
__device__ __forceinline__ uint32_t pack2(float lo, float hi) {
  uint32_t r; asm("cvt.rn.bf16x2.f32 %0, %1, %2;" : "=r"(r) : "f"(hi), "f"(lo)); return r;
}
__device__ __forceinline__ float bf_lo(uint32_t w) { return __uint_as_float(w << 16); }
__device__ __forceinline__ float bf_hi(uint32_t w) { return __uint_as_float(w & 0xffff0000u); }
__device__ __forceinline__ float tanh_fast(float x) { float y; asm("tanh.approx.f32 %0, %1;" : "=f"(y) : "f"(x)); return y; }
__device__ __forceinline__ float ex2_fast(float x) { float y; asm("ex2.approx.ftz.f32 %0, %1;" : "=f"(y) : "f"(x)); return y; }
template <uint32_t HI = 0x40000040u>
__device__ __forceinline__ uint64_t desc_lo(uint32_t lo) { uint64_t d; asm("mov.b64 %0, {%1, %2};" : "=l"(d) : "r"(lo), "r"(HI)); return d; }
__device__ __forceinline__ uint4 lds128(uint32_t a) { uint4 v; asm volatile("ld.shared.v4.u32 {%0,%1,%2,%3}, [%4];" : "=r"(v.x), "=r"(v.y), "=r"(v.z), "=r"(v.w) : "r"(a) : "memory"); return v; }
__device__ __forceinline__ void stsm4(uint32_t a, uint32_t r0, uint32_t r1, uint32_t r2, uint32_t r3) {
  asm volatile("stmatrix.sync.aligned.m8n8.x4.shared.b16 [%0], {%1,%2,%3,%4};" ::"r"(a), "r"(r0), "r"(r1), "r"(r2), "r"(r3) : "memory");
}
__device__ __forceinline__ void tma2d(uint32_t dst, const CUtensorMap* tm, uint32_t bar, int c0, int c1) {
  asm volatile("cp.async.bulk.tensor.2d.shared::cluster.global.mbarrier::complete_tx::bytes [%0], [%1, {%3,%4}], [%2];" ::"r"(dst), "l"(tm), "r"(bar), "r"(c0), "r"(c1) : "memory");
}
__device__ __forceinline__ void tma3d(uint32_t dst, const CUtensorMap* tm, uint32_t bar, int c0, int c1, int c2) {
  asm volatile("cp.async.bulk.tensor.3d.shared::cluster.global.mbarrier::complete_tx::bytes [%0], [%1, {%3,%4,%5}], [%2];" ::"r"(dst), "l"(tm), "r"(bar), "r"(c0), "r"(c1), "r"(c2) : "memory");
}
__device__ __forceinline__ void publish(unsigned* p) {
  if (REL) asm volatile("red.release.gpu.global.add.u32 [%0], 1;" ::"l"(p) : "memory");
  else { __threadfence(); asm volatile("red.relaxed.gpu.global.add.u32 [%0], 1;" ::"l"(p) : "memory"); }
}
__device__ __forceinline__ void poll_ge(const unsigned* p, unsigned target) {
  unsigned v, n = 0;
#pragma unroll 1
  while (true) {
    asm volatile("ld.acquire.gpu.global.u32 %0, [%1];" : "=r"(v) : "l"(p) : "memory");
    if (v >= target) break;
    if (++n > (1u << 22)) { die(); break; }
  }
}
__device__ __forceinline__ uint32_t hadd2(uint32_t a, uint32_t b) { uint32_t r; asm("add.rn.bf16x2 %0, %1, %2;" : "=r"(r) : "r"(a), "r"(b)); return r; }
__device__ __forceinline__ uint32_t hfma2(uint32_t a, uint32_t b, uint32_t c) { uint32_t r; asm("fma.rn.bf16x2 %0, %1, %2, %3;" : "=r"(r) : "r"(a), "r"(b), "r"(c)); return r; }
__device__ __forceinline__ uint32_t hmul2(uint32_t a, uint32_t b) { uint32_t r; asm("mul.rn.bf16x2 %0, %1, %2;" : "=r"(r) : "r"(a), "r"(b)); return r; }
__device__ __forceinline__ float gelu_s(float g0, float k0, float k1, float k2) {
  float p = fmaf(g0 * g0, k1, k0);
  float th = tanh_fast(g0 * p);
  return g0 * fmaf(th, k2, k2);
}
__device__ __forceinline__ float phi(float t0, float rstd, float rl2e) {
  float e;
  asm("add.sat.f32 %0, %1, 0f358637BD;" : "=f"(e) : "f"(ex2_fast(t0 * rl2e)));
  return fmaf(fmaxf(t0, 0.f), rstd, e);
}
__device__ __forceinline__ void wgmma_tf32_n32(float (&d)[16], float a0, float a1, float a2, float a3, uint64_t db, int sd) {
  asm volatile("{\n.reg .pred p;\nsetp.ne.b32 p, %21, 0;\n"
    "wgmma.mma_async.sync.aligned.m64n32k8.f32.tf32.tf32 {%0,%1,%2,%3,%4,%5,%6,%7,%8,%9,%10,%11,%12,%13,%14,%15}, {%16,%17,%18,%19}, %20, p, 1, 1;\n}\n"
    : "+f"(d[0]), "+f"(d[1]), "+f"(d[2]), "+f"(d[3]), "+f"(d[4]), "+f"(d[5]), "+f"(d[6]), "+f"(d[7]),
      "+f"(d[8]), "+f"(d[9]), "+f"(d[10]), "+f"(d[11]), "+f"(d[12]), "+f"(d[13]), "+f"(d[14]), "+f"(d[15])
    : "r"(__float_as_uint(a0)), "r"(__float_as_uint(a1)), "r"(__float_as_uint(a2)), "r"(__float_as_uint(a3)), "l"(db), "r"(sd));
}
__device__ __forceinline__ void mma_rs(float (&d)[32], const uint32_t* a, uint64_t b, int sd) { wgmma_rs_n64(d, a[0], a[1], a[2], a[3], b, sd); }
__device__ __forceinline__ void mma_rs(float (&d)[28], const uint32_t* a, uint64_t b, int sd) { wgmma_rs_n56(d, a[0], a[1], a[2], a[3], b, sd); }
template <int N> __device__ __forceinline__ void keep(uint32_t* d) {
#pragma unroll
  for (int i = 0; i < N; i++) asm volatile("" : "+r"(d[i])::"memory");
}

template <int N> struct ic { static constexpr int value = N; };
struct Ctx { uint32_t bar, ok; int lane, wg; };
template <int I> __device__ __forceinline__ void release(const Ctx& C) { if (C.lane == 0) mbar_arrive(C.bar + (B_EMPTY + (I & 7)) * 8); }
template <int I, bool SW64 = false, int NA>
__device__ __forceinline__ void grp(float (&acc)[NA], const uint32_t (&xf)[112], uint32_t d, Ctx& C) {
  mbar_ensure(C.ok, C.bar + (B_FULL + (I & 7)) * 8, (I / 8 + 1) & 1);
  C.ok = mbar_probe(C.bar + (B_FULL + ((I + 1) & 7)) * 8, ((I + 1) / 8 + 1) & 1);
  if ((I & 3) == 0) TLREC(C.wg, 20 + I / 4);
  WG_FENCE;
#pragma unroll
  for (int k = 0; k < 7; k++)
    mma_rs(acc, &xf[((I & 3) * 7 + k) * 4], desc_lo<SW64 ? 0x80000020u : 0x40000040u>(d + (I & 7) * (SLOT >> 4) + k * (SW64 ? 64 : 128)), (I & 3) + k);
  WG_COMMIT;
}
template <int I, bool SW64 = false, int NA, int NP, class E0, class E1, class E2, class E3>
__device__ __forceinline__ void pass(float (&acc)[NA], float (&prev)[NP], const uint32_t (&xf)[112], uint32_t d, Ctx& C, E0 e0, E1 e1, E2 e2, E3 e3) {
  grp<I, SW64>(acc, xf, d, C);
  e0();
  if constexpr (I > 0) { WG_WAIT(1); release<I - 1>(C); fence_regs(prev); }
  grp<I + 1, SW64>(acc, xf, d, C);
  e1();
  WG_WAIT(1); release<I>(C);
  grp<I + 2, SW64>(acc, xf, d, C);
  e2();
  WG_WAIT(1); release<I + 1>(C);
  grp<I + 3, SW64>(acc, xf, d, C);
  e3();
  WG_WAIT(1); release<I + 2>(C);
}

struct G2State { uint32_t o2, land, rbar, stg; bool lead; };
template <int I, int ST>
__device__ __forceinline__ void g2_issue(float (&acc)[32], const uint32_t (&ha)[72], Ctx& C, const G2State& S) {
  mbar_ensure(C.ok, C.bar + (B_FULL + (I & 7)) * 8, (I / 8 + 1) & 1);
  if (I + 1 < I_G2 + 21) C.ok = mbar_probe(C.bar + (B_FULL + ((I + 1) & 7)) * 8, ((I + 1) / 8 + 1) & 1);
  constexpr uint32_t db = DRING + (I & 7) * (SLOT >> 4);
  WG_FENCE;
#pragma unroll
  for (int k = 0; k < 6; k++) {
    const int kk = ST * 6 + k;
    const uint32_t d = ST > 0 ? db + k * 128 : (k < 4 ? db + S.o2 + k * 128 : db - 2 * S.o2 + k * 128);
    wgmma_rs_n64(acc, ha[kk * 4], ha[kk * 4 + 1], ha[kk * 4 + 2], ha[kk * 4 + 3], desc_lo(d), kk);
  }
  WG_COMMIT;
}
template <int I> __device__ __forceinline__ void g2_done(const Ctx& C) { WG_WAIT(1); if (I + 8 < I_G2 + 21) release<I>(C); }
__device__ __forceinline__ void g2_fetch(uint32_t (&v)[16], const Ctx& C, const G2State& S, uint32_t okl, int c) {
  if (!S.lead) {
    mbar_ensure(okl, C.bar + (B_LAND + c) * 8, 0);
#pragma unroll
    for (int q = 0; q < 4; q++) { const uint4 u = lds128(S.land + c * 8192 + q * 2048); v[q * 4] = u.x; v[q * 4 + 1] = u.y; v[q * 4 + 2] = u.z; v[q * 4 + 3] = u.w; }
  }
}
__device__ __forceinline__ void g2_out(float (&cur)[32], const uint32_t (&v)[16], const Ctx& C, const G2State& S, int c, __nv_bfloat16* const* outp) {
  uint32_t w[16];
#pragma unroll
  for (int j = 0; j < 16; j++) w[j] = pack2(cur[j * 2], cur[j * 2 + 1]);
  if (S.lead) {
#pragma unroll
    for (int q = 0; q < 4; q++)
      asm volatile("st.async.shared::cluster.mbarrier::complete_tx::bytes.v4.u32 [%0], {%1,%2,%3,%4}, [%5];"
                   ::"r"(S.land + c * 8192 + q * 2048), "r"(w[q * 4]), "r"(w[q * 4 + 1]), "r"(w[q * 4 + 2]), "r"(w[q * 4 + 3]), "r"(S.rbar + c * 8) : "memory");
  } else {
#pragma unroll
    for (int q = 0; q < 4; q++)
      stsm4((S.stg ^ (q << 5)) + c * 8192, hadd2(w[q * 4], v[q * 4]), hadd2(w[q * 4 + 1], v[q * 4 + 1]), hadd2(w[q * 4 + 2], v[q * 4 + 2]), hadd2(w[q * 4 + 3], v[q * 4 + 3]));
    __syncwarp();
    if (c < 7 - DRED) {
      if (C.lane == 0) mbar_arrive(C.bar + (B_STG + c) * 8);
    } else {
      const uint32_t bx = blockIdx.x, row = ((threadIdx.x >> 1) & 48) + (C.lane >> 3);
      const uint32_t a = C.bar - OFF_BAR + (bx & 1) * XW_BYTES + c * 8192 + row * 128 + (C.lane & 7) * 16;
      char* g = (char*)*outp + ((bx >> 3) * 128 + (bx & 1) * 64 + row) * 896 + c * 128;
#pragma unroll
      for (int i = 0; i < 4; i++) {
        const uint4 u = lds128(a + i * 512);
        asm volatile("red.relaxed.gpu.global.add.noftz.v4.bf16x2 [%0], {%1,%2,%3,%4};" ::"l"(g + i * 3584 + (((C.lane ^ row ^ (i * 4)) & 7) << 4)), "r"(u.x), "r"(u.y), "r"(u.z), "r"(u.w) : "memory");
      }
    }
  }
}
template <int c>
__device__ __forceinline__ void g2_step(float (&cur)[32], float (&nxt)[32], uint32_t (&v)[16], const uint32_t (&ha)[72], Ctx& C, const G2State& S, __nv_bfloat16* const* outp) {
  constexpr int I = I_G2 + 3 * c + 3;
  fence_regs(cur);
  if constexpr (c > 0) {
    if constexpr (c < 6) g2_issue<I + 1, 1>(nxt, ha, C, S);
    g2_out(cur, v, C, S, c, outp);
    if constexpr (c < 6) g2_done<I>(C);
  }
  if constexpr (c < 6) {
    const uint32_t okl = mbar_probe(C.bar + (B_LAND + c + 1) * 8, 0);
    g2_issue<I + 2, 2>(nxt, ha, C, S);
    if (c == 0) g2_out(cur, v, C, S, c, outp);
    if constexpr (c < 5) {
      g2_done<I + 1>(C);
      g2_issue<I + 3, 0>(cur, ha, C, S);
      g2_fetch(v, C, S, okl, c + 1);
      g2_done<I + 2>(C);
    } else {
      g2_fetch(v, C, S, okl, c + 1);
      WG_WAIT(0);
    }
  }
  TLREC(C.wg, 10 + c);
}
__device__ __forceinline__ void cp16(uint32_t dst, const void* src) { asm volatile("cp.async.cg.shared.global [%0], [%1], 16;" ::"r"(dst), "l"(src) : "memory"); }
template <int N> __device__ __forceinline__ void cp_wait() { asm volatile("cp.async.wait_group %0;" ::"n"(N) : "memory"); __syncwarp(); }
__device__ __forceinline__ bool elect() {
  uint32_t el;
  asm volatile("{\n.reg .pred p;\nelect.sync _|p, 0xffffffff;\nselp.u32 %0, 1, 0, p;\n}" : "=r"(el));
  return el;
}
template <int I>
__device__ __forceinline__ void fill(const Params& P, uint32_t sb, int r, int s) {
  const uint32_t fb = sb + OFF_BAR + (B_FULL + (I & 7)) * 8, dst = sb + OFF_RING + (I & 7) * SLOT;
  const int Rb = 224 * s, Rr = Rb + 96 * r;
  if (I >= 8) mbar_wait(fb + (B_EMPTY - B_FULL) * 8, ((I >> 3) - 1) & 1);
  if constexpr (I < I_G2) {
    constexpr int ps = I >> 2, row = (I & 3) * 112;
    mbar_expect(fb, SLOT);
    if (ps == 2 || ps == 3 || ps == 9) tma2d(dst, &P.tmQ, fb, 56 * s - 8 * r + (ps == 9 ? 0 : 448 * (ps - 1)), row);
    else if (ps == 8) { tma2d(dst, &P.tmG32, fb, Rb + 192 - 192 * r, row); tma2d(dst + SLOT / 2, &P.tmU32, fb, Rb + 192 - 192 * r, row); }
    else tma2d(dst, (ps & 1) ? &P.tmU : &P.tmG, fb, ps < 2 ? Rr : (ps < 6 ? Rr + 64 : Rb + 128 - 96 * r), row);
    if ((I & 3) == 1) TLREC(2, 20 + ps);
  } else {
    constexpr int J = I - I_G2 == 2 ? 3 : (I - I_G2 == 3 ? 2 : I - I_G2), st = J % 3, c = (J / 3) * 64;
    mbar_expect(fb, 12288);
    if (st < 2) tma2d(dst, &P.tmWd96, fb, c, st ? Rr : Rb + 128 - 128 * r);
    else { tma2d(dst, &P.tmWd32, fb, c, Rr + 96); tma3d(dst + 4096, &P.tmWo, fb, c, 0, 2 * s); }
  }
}
template <int I>
__device__ __forceinline__ void fill_from(const Params& P, uint32_t sb, int r, int s) {
  if constexpr (I < I_G2 + 21) { fill<I>(P, sb, r, s); fill_from<I + 2>(P, sb, r, s); }
}
template <int W> __device__ __forceinline__ void init_bars(int wid, uint32_t bar) {
  if constexpr (W < 3) {
    if (wid == W) {
#pragma unroll
      for (int i = W; i < B_CH; i += 3) {
        mbar_init(bar + i * 8, (i >= B_EMPTY && i < B_LAND) ? 8 : (i == B_PEER || i == B_KV || i == B_KV + 1 || (i >= B_STG && i < B_CS) ? 4 : (DRED > 0 && i == B_LAND + 7 - DRED ? 2 : 1)));
        if (i >= B_LAND && i < B_PEER) mbar_expect(bar + i * 8, 8192);
      }
    } else init_bars<W + 1>(wid, bar);
  }
}
__global__ void __cluster_dims__(2, 1, 1) __launch_bounds__(384, 1) fused_kernel(const __grid_constant__ Params P) {
  extern __shared__ __align__(1024) uint8_t smem_raw[];
  const uint32_t sb = smem_u32(smem_raw);
  const uint32_t bar = sb + OFF_BAR;
  const int tid = threadIdx.x, b = blockIdx.x;
  const int r = b & 1, m = b >> 3, s = b & 7;
  const int wid = __shfl_sync(~0u, tid >> 5, 0), wg = wid >> 2;

  if (wg < 2) {
    TLREC(wg, 41);
    const uint32_t swz = (((tid ^ (tid >> 3)) & 3) << 4) + ((tid & 4) << 4);
    const int rw = (wid & 3) * 16 + ((tid & 31) >> 3);
    const char* sx = (const char*)P.x + (m * 128 + wg * 64 + rw) * 896 + (tid & 7) * 16;
    const char* sw = (const char*)(wg ? P.wg : P.wu) + rw * 3584 + (224 * s + 96 * r) * 2 + (tid & 7) * 16;
    const uint32_t dx = sb + wg * XW_BYTES + rw * 128 + swz, dw = sb + OFF_RING + wg * 8192 + rw * 128 + swz;
#pragma unroll
    for (int c = 0; c < NCP; c++) {
#pragma unroll
      for (int i = 0; i < 4; i++) cp16((dx ^ ((i & 1) << 6)) + c * 8192 + i * 512, sx + c * 128 + i * 3584);
#pragma unroll
      for (int i = 0; i < 4; i++) cp16((dw ^ ((i & 1) << 6)) + c * 16384 + i * 512, sw + (c * 64 + i * 4) * 3584);
      asm volatile("cp.async.commit_group;" ::: "memory");
    }
    if (PF0 > 0 && wid < PF0) {
      const int l = tid & 31, c = NCP + wid;
      const char* p = l < 16 ? (const char*)P.x + (m * 128 + s * 16 + l) * 896 + c * 128
                             : (const char*)((l & 4) ? P.wg : P.wu) + (c * 64 + m * 4 + (l & 3)) * 3584 + (224 * s + 96 * r) * 2;
      if (l < 24) asm volatile("prefetch.global.L2 [%0];" ::"l"(p) : "memory");
    }
    TLREC(wg, 43);
  }
  auto chunk_tma = [&](int c) {
    const uint32_t fb = bar + (B_CH + c) * 8;
    mbar_expect(fb, 32768);
    tma2d(sb + c * 8192, &P.tmX, fb, c * 64, m * 128);
    tma2d(sb + XW_BYTES + c * 8192, &P.tmX, fb, c * 64, m * 128 + 64);
    tma2d(sb + OFF_RING + c * 16384, &P.tmU64, fb, 224 * s + 96 * r, c * 64);
    tma2d(sb + OFF_RING + c * 16384 + 8192, &P.tmG64, fb, 224 * s + 96 * r, c * 64);
  };
  if (wg == 2) {
    asm volatile("setmaxnreg.dec.sync.aligned.u32 40;");
    if (elect()) {
      if (wid == 8) {
#pragma unroll
        for (int c = NCP; c < 7; c++) mbar_init(bar + (B_CH + c) * 8, 1);
        if (ETMA > 0) FENCE_ASYNC_SMEM;
        TLREC(2, 38);
#pragma unroll
        for (int c = NCP; c < NCP + ETMA; c++) chunk_tma(c);
      } else {
        asm volatile("prefetch.tensormap [%0];" ::"l"(&P.tmX + (wid - 9)) : "memory");
        init_bars<0>(wid - 9, bar);
        if ((sb & 0x3FFFF) != SB0) die();
      }
      asm volatile("fence.mbarrier_init.release.cluster;" ::: "memory");
      FENCE_ASYNC_SMEM;
    }
    __syncwarp();
  }
  asm volatile("barrier.cluster.arrive.relaxed.aligned;" ::: "memory");

  if (wg == 2) {
    if (wid == 8 && elect()) {
      TLREC(2, 39);
#pragma unroll
      for (int c = NCP + ETMA; c < 7; c++) chunk_tma(c);
      TLREC(2, 40);
    }
    __syncwarp();
    asm volatile("barrier.cluster.wait.aligned;" ::: "memory");
    if (wid < 10) {
      if (elect()) {
        if (wid == 8) fill_from<8>(P, sb, r, s); else fill_from<9>(P, sb, r, s);
      }
    } else if (tid >= 320) {
      const int h = tid - 320;
      const unsigned ep = g_epoch[b];
      const unsigned par = ep & 1;
      const int Rb = 224 * s, Rr = Rb + 96 * r;
      auto pf = [](const char* p) { asm volatile("prefetch.global.L2 [%0];" ::"l"(p) : "memory"); };
      const int wrow = m * 28 + ((h & 31) < 28 ? (h & 31) : 27);
      const char* pg = (const char*)P.wg + wrow * 3584;
      const char* pu = (const char*)P.wu + wrow * 3584;
      const char* pq = (const char*)P.wqkv + wrow * 2688 + 112 * s;
      if (h == 0) asm volatile("prefetch.tensormap [%0];" ::"l"(&P.tmQ) : "memory");
      mbar_wait(bar + (B_CH + KV_AT) * 8, 0);
      pf(pq + (h < 32 ? 896 : 1792)); pf(pq + (h < 32 ? 896 : 1792) + 111);
      mbar_wait(bar + (B_CH + CS_AT) * 8, 0);
      pf((h < 32 ? pg : pu) + Rr * 2 + 128);
      {
        const char* p = (const char*)((h & 8) ? P.wu : P.wg) + (m * 28 + (h >> 4) * 7) * 3584 + Rr * 2 + (h & 7) * 16;
        float a[8];
#pragma unroll
        for (int j = 0; j < 8; j++) a[j] = 0.f;
#pragma unroll
        for (int o = 0; o < 7; o += 4) {
          uint4 cw[4];
#pragma unroll
          for (int i = 0; i < 4; i++) if (o + i < 7) cw[i] = __ldcg((const uint4*)(p + (o + i) * 3584));
#pragma unroll
          for (int j = 0; j < 8; j++)
#pragma unroll
            for (int i = 0; i < 4; i++) if (o + i < 7) { const uint32_t w = (&cw[i].x)[j >> 1]; a[j] += (j & 1) ? bf_hi(w) : bf_lo(w); }
          fence_regs(a);
        }
        const bool up = h & 16;
#pragma unroll
        for (int j = 0; j < 4; j++) a[j] = (up ? a[j + 4] : a[j]) + __shfl_xor_sync(~0u, up ? a[j] : a[j + 4], 16);
        asm volatile("red.relaxed.gpu.global.add.v4.f32 [%0], {%1,%2,%3,%4};" ::"l"(&g_cs[par][s][(h & 15) * 8 + (up ? 4 : 0)]), "f"(a[0]), "f"(a[1]), "f"(a[2]), "f"(a[3]) : "memory");
        if ((EPF & 1) && h >= 32) { pf(pg + Rb * 2 + 256 - 192 * r); pf(pu + Rb * 2 + 256 - 192 * r); pf(pg + Rb * 2 + 384 - 384 * r); pf(pu + Rb * 2 + 384 - 384 * r); pf(pq); pf(pq + 111); }
        if ((EPF & 2) && h == 0) {
          asm volatile("prefetch.tensormap [%0];" ::"l"(&P.tmG) : "memory");
          asm volatile("prefetch.tensormap [%0];" ::"l"(&P.tmU) : "memory");
        }
        __syncwarp();
        if ((h & 31) == 0) {
          if (h == 0) TLREC(2, 30);
          publish(&g_cnt[par][24 + s]);
          if (h == 0) TLREC(2, 31);
        }
        __syncwarp();
      }
      if (h < 32) {
        *(float4*)&g_kv[par ^ 1][s][m * 128 + h * 4] = make_float4(0.f, 0.f, 0.f, 0.f);
        if (m == 0) *(float4*)&g_cs[par ^ 1][s][h * 4] = make_float4(0.f, 0.f, 0.f, 0.f);
        if (h == 0) {
          if (b < 32) g_cnt[par ^ 1][b] = 0;
          asm volatile("prefetch.tensormap [%0];" ::"l"(&P.tmG) : "memory");
          asm volatile("prefetch.tensormap [%0];" ::"l"(&P.tmU) : "memory");
          asm volatile("prefetch.tensormap [%0];" ::"l"(&P.tmG32) : "memory");
          asm volatile("prefetch.tensormap [%0];" ::"l"(&P.tmU32) : "memory");
          asm volatile("prefetch.tensormap [%0];" ::"l"(&P.tmWd96) : "memory");
          asm volatile("prefetch.tensormap [%0];" ::"l"(&P.tmWd32) : "memory");
          asm volatile("prefetch.tensormap [%0];" ::"l"(&P.tmWo) : "memory");
          asm volatile("prefetch.tensormap [%0];" ::"l"(&P.tmOut) : "memory");
#pragma unroll 1
          for (int j = 0; j < 2; j++) {
            mbar_wait(bar + (B_KV + j) * 8, 0);
            FENCE_ASYNC_SMEM;
            asm volatile("cp.reduce.async.bulk.global.shared::cta.bulk_group.add.f32 [%0], [%1], %2;" ::"l"(&g_kv[par][s][0]),
                         "r"(sb + (r ^ 1 ^ j) * XW_BYTES + XO_KV), "r"(8192) : "memory");
            asm volatile("cp.async.bulk.commit_group;" ::: "memory");
          }
          TLREC(2, 6);
          asm volatile("cp.async.bulk.wait_group 0;" ::: "memory");
          TLREC(2, 2);
          FENCE_ASYNC_GLOBAL;
          publish(&g_cnt[par][s]);
          TLREC(2, 7);
          poll_ge(&g_cnt[par][s], 16);
          FENCE_ASYNC_GLOBAL;
          TLREC(2, 8);
          mbar_expect(bar + B_KVD * 8, 8192);
          asm volatile("cp.async.bulk.shared::cluster.global.mbarrier::complete_tx::bytes [%0], [%1], %2, [%3];" ::"r"(sb + r * XW_BYTES + XO_KVD),
                       "l"(&g_kv[par][s][0]), "r"(8192), "r"(bar + B_KVD * 8) : "memory");
          g_epoch[b] = ep + 1;
        }
      } else {
        const int l = h - 32;
        auto copy = [&](int i) {
          const size_t o = (size_t)b * 14336 + i * 2048 + l * 16;
          uint4 v[4];
#pragma unroll
          for (int j = 0; j < 4; j++) v[j] = __ldcg((const uint4*)((const char*)P.x + o + j * 512));
#pragma unroll
          for (int j = 0; j < 4; j++) __stcg((uint4*)((char*)P.out + o + j * 512), v[j]);
        };
        auto pfd = [&] {
#pragma unroll
        for (int j = 0; j < 4; j++) if (j < 3 || l < 2) pf((const char*)P.wd + (s * 16 + m) * 12544 + j * 4096 + l * 128);
        if (l < 25) pf((const char*)P.wo + (s * 16 + m) * 3136 + l * 128);
        };
        copy(0);
        if (EPF & 4) pfd();
        if (!(EPF & 1)) { pf(pg + Rb * 2 + 256 - 192 * r); pf(pu + Rb * 2 + 256 - 192 * r); pf(pg + Rb * 2 + 384 - 384 * r); pf(pu + Rb * 2 + 384 - 384 * r); pf(pq); pf(pq + 111); }
        if (l == 0) { poll_ge(&g_cnt[par][24 + s], 32); TLREC(2, 32); }
        __syncwarp();
        {
          const float4 v = __ldcg((const float4*)&g_cs[par][s][l * 4]);
          const uint32_t a = sb + OFF_CS + ((l >> 2) & 3) * 64 + (l & 1) * 32 + (l >> 4) * 8 + (l & 2) * 2;
          asm volatile("st.shared.u32 [%0], %1;" ::"r"(a), "r"(pack2(v.x, v.y)) : "memory");
          asm volatile("st.shared.u32 [%0], %1;" ::"r"(a + 16), "r"(pack2(v.z, v.w)) : "memory");
          __syncwarp();
          if (l == 0) mbar_arrive(bar + B_CS * 8);
          if (l == 0) TLREC(2, 33);
        }
        copy(1); copy(2); copy(3);
        if (!(EPF & 4)) pfd();
        copy(4); copy(5); copy(6);
        __syncwarp();
        if (l) return;
        publish(&g_cnt[par][8 + m]);
        mbar_wait(bar + B_KV * 8, 0);
        poll_ge(&g_cnt[par][8 + m], 8);
        if (DRED > 0) mbar_arrive(bar + (B_LAND + 7 - DRED) * 8);
        FENCE_ASYNC_GLOBAL;
#pragma unroll 1
        for (int c = 0; c < 7 - DRED; c++) {
          mbar_wait(bar + (B_STG + c) * 8, 0);
          FENCE_ASYNC_SMEM;
          asm volatile("cp.reduce.async.bulk.tensor.2d.global.shared::cta.add.bulk_group [%0, {%2,%3}], [%1];" ::"l"(&P.tmOut), "r"(sb + r * XW_BYTES + c * 8192), "r"(c * 64), "r"(m * 128 + r * 64) : "memory");
          asm volatile("cp.async.bulk.commit_group;" ::: "memory");
        }
        TLREC(2, 16);
        asm volatile("cp.async.bulk.wait_group.read 0;" ::: "memory");
        TLREC(2, 17);
      }
    }
  } else {
    asm volatile("setmaxnreg.inc.sync.aligned.u32 232;");
    uint32_t bar;
    asm volatile("add.u32 %0, %1, %2;" : "=r"(bar) : "r"(sb), "n"(OFF_BAR));
    const int lane = tid & 31, warp = wid & 3, t = lane & 3;
    const bool lead = (wg != r);
    const uint32_t xw = sb + wg * XW_BYTES;
    constexpr uint32_t dB = DRING;
    const int row = warp * 16 + (lane & 15);
    const uint32_t frag = xw + row * 128 + (((lane >> 4) ^ (row & 7)) << 4);
    const uint32_t park = xw + XO_PARK + (tid & 127) * 16;
    Ctx C{bar, 0u, lane, wg};
    uint32_t xf[112];
    float rstd[2];
    uint32_t nm[2];
    TLREC(wg, 0); TLREG(wg, 62);
    auto ldx = [&](int k0, int k1) {
#pragma unroll
      for (int k = k0; k < k1; k++) {
        uint32_t* f = &xf[k * 4];
        asm volatile("ldmatrix.sync.aligned.m8n8.x4.shared.b16 {%0,%1,%2,%3}, [%4];" : "=r"(f[0]), "=r"(f[1]), "=r"(f[2]), "=r"(f[3]) : "r"((frag ^ ((k & 3) << 5)) + (k >> 2) * 8192) : "memory");
      }
    };
    auto center = [&](int o, int n) {
#pragma unroll
      for (int k = o; k < o + n; k++) { xf[k] = hadd2(xf[k], nm[k & 1]); keep<1>(xf + k); }
    };
    float acc0[32], acc1[32];
    float st[4] = {0.f, 0.f, 0.f, 0.f};
    {
      auto hmma = [&](float* e, uint32_t a0, uint32_t a1, uint32_t a2, uint32_t a3, uint32_t b0, uint32_t b1) {
        asm volatile("mma.sync.aligned.m16n8k16.row.col.f32.bf16.bf16.f32 {%0,%1,%2,%3}, {%4,%5,%6,%7}, {%8,%9}, {%0,%1,%2,%3};"
                     : "+f"(e[0]), "+f"(e[1]), "+f"(e[2]), "+f"(e[3]) : "r"(a0), "r"(a1), "r"(a2), "r"(a3), "r"(b0), "r"(b1));
      };
      const uint32_t be = (lane & 4) ? 0u : 0x3F803F80u;
      float tl[4];
      auto stats = [&](int c) {
        uint32_t sm[2], sq[2];
#pragma unroll
        for (int j = 0; j < 2; j++) {
          const uint32_t* f = &xf[c * 16 + j];
          sq[j] = hmul2(f[0], f[0]);
#pragma unroll
          for (int k = 1; k < 8; k++) sq[j] = hfma2(f[k * 2], f[k * 2], sq[j]);
          sm[j] = hadd2(hadd2(hadd2(f[0], f[2]), hadd2(f[4], f[6])), hadd2(hadd2(f[8], f[10]), hadd2(f[12], f[14])));
        }
        if (c < 7 - LS) hmma(st, sm[0], sm[1], sq[0], sq[1], be, be ^ 0x3F803F80u);
        else {
#pragma unroll
          for (int j = 0; j < 4; j++) {
            const uint32_t w = (j & 1) ? sq[j >> 1] : sm[j >> 1];
            const float v = bf_lo(w) + bf_hi(w);
            tl[j] = c == 7 - LS ? v : tl[j] + v;
          }
          if (c == 6) {
#pragma unroll
            for (int j = 0; j < 4; j++) tl[(j >> 1) + (j & 1) * 2] += __shfl_xor_sync(~0u, tl[(j >> 1) + (j & 1) * 2], 1);
#pragma unroll
            for (int j = 0; j < 4; j++) st[(j >> 1) + (j & 1) * 2] += tl[(j >> 1) + (j & 1) * 2] + __shfl_xor_sync(~0u, tl[(j >> 1) + (j & 1) * 2], 2);
          }
        }
      };
      auto chunk = [&](auto cc) {
        constexpr int c = decltype(cc)::value;
        if constexpr (c < NCP) cp_wait<NCP - 1 - c>(); else mbar_wait(bar + (B_CH + c) * 8, 0);
        TLREC(wg, 48 + c);
        ldx(c * 4, c * 4 + 4);
        if (c < NCP) FENCE_ASYNC_SMEM;
        if (c == 0) {
          float d[2][4] = {};
#pragma unroll
          for (int k = 0; k < 4; k++) hmma(d[k & 1], xf[k * 4], xf[k * 4 + 1], xf[k * 4 + 2], xf[k * 4 + 3], 0x3F803F80u, 0x3F803F80u);
#pragma unroll
          for (int j = 0; j < 2; j++) { const float v = (d[0][2 * j] + d[1][2 * j]) * (-1.0f / 64.0f); nm[j] = pack2(v, v); }
        }
        center(c * 16, 16);
        if (G6 && c == 6) {
          uint32_t sm[2];
#pragma unroll
          for (int j = 0; j < 2; j++) {
            const uint32_t* f = &xf[c * 16 + j];
            sm[j] = hadd2(hadd2(hadd2(f[0], f[2]), hadd2(f[4], f[6])), hadd2(hadd2(f[8], f[10]), hadd2(f[12], f[14])));
          }
          if (G6 == 1) {
            if (!lead) bar_sync(6 + c, 256);
            hmma(st, sm[0], sm[1], 0u, 0u, be, 0u);
          } else {
#pragma unroll
            for (int j = 0; j < 2; j++) { tl[j] = bf_lo(sm[j]) + bf_hi(sm[j]); tl[j] += __shfl_xor_sync(~0u, tl[j], 1); }
#pragma unroll
            for (int j = 0; j < 2; j++) st[2 * j] += tl[j] + __shfl_xor_sync(~0u, tl[j], 2);
            fence_regs(st);
          }
        }
        if (c < NCP) bar_sync(2, 256);
        if (!lead && !(G6 == 1 && c == 6)) bar_sync(6 + c, 256);
        WG_FENCE;
#pragma unroll
        for (int k = c * 4; k < c * 4 + 4; k++) mma_rs(acc0, &xf[k * 4], desc_lo(dB + c * 1024 + (k & 3) * 128), k);
        if (c == 6) WG_COMMIT;
#pragma unroll
        for (int k = c * 4; k < c * 4 + 4; k++) mma_rs(acc1, &xf[k * 4], desc_lo(dB + c * 1024 + 512 + (k & 3) * 128), k);
        WG_COMMIT;
        if (lead) asm volatile("bar.arrive %0, 256;" ::"n"(6 + c) : "memory");
        if (c == 0) asm volatile("barrier.cluster.wait.aligned;" ::: "memory");
        if constexpr (c > 0) { if (c < 6) WG_WAIT(1); else WG_WAIT(2); release<c - 1>(C); }
        if (!(G6 && c == 6)) stats(c);
      };
      chunk(ic<0>{}); chunk(ic<1>{}); chunk(ic<2>{}); chunk(ic<3>{}); chunk(ic<4>{}); chunk(ic<5>{}); chunk(ic<6>{});
      TLREC(wg, 1);
    }
    auto park_raw = [&](float (&a)[32], uint32_t o) {
#pragma unroll
      for (int q = 0; q < 4; q++)
        asm volatile("st.shared.v4.u32 [%0], {%1,%2,%3,%4};" ::"r"(park + o + q * 2048), "r"(pack2(a[q * 8], a[q * 8 + 1])), "r"(pack2(a[q * 8 + 2], a[q * 8 + 3])),
                     "r"(pack2(a[q * 8 + 4], a[q * 8 + 5])), "r"(pack2(a[q * 8 + 6], a[q * 8 + 7])) : "memory");
    };
    auto nop = [] {};
    auto gelu_part = [&](float (&a)[32], uint32_t* gl, int j0, int j1) {
      float k0[2], k1[2], k2[2];
#pragma unroll
      for (int j = 0; j < 2; j++) { k0[j] = 0.7978845608f * rstd[j]; k2[j] = 0.5f * rstd[j] * rstd[j]; k1[j] = 0.0713548162f * rstd[j] * k2[j]; }
#pragma unroll
      for (int j = j0; j < j1; j++) {
        gl[j] = pack2(gelu_s(a[j * 2], k0[j & 1], k1[j & 1], k2[j & 1]), gelu_s(a[j * 2 + 1], k0[j & 1], k1[j & 1], k2[j & 1]));
        asm volatile("" : "+r"(gl[j])::"memory");
      }
    };
    auto mul_up = [&](float (&a)[32], uint32_t* gl) {
#pragma unroll
      for (int j = 0; j < 16; j++) gl[j] = hmul2(gl[j], pack2(a[j * 2], a[j * 2 + 1]));
    };
    auto park_h = [&](const uint32_t* h, int o) {
#pragma unroll
      for (int q = 0; q < 4; q++)
        asm volatile("st.shared.v4.u32 [%0], {%1,%2,%3,%4};" ::"r"(park + (o + q) * 2048), "r"(h[q * 4]), "r"(h[q * 4 + 1]), "r"(h[q * 4 + 2]), "r"(h[q * 4 + 3]) : "memory");
    };
    auto unpark_h = [&](uint32_t* h, int o) {
#pragma unroll
      for (int q = 0; q < 4; q++) { const uint4 v = lds128(park + (o + q) * 2048); h[q * 4] = v.x; h[q * 4 + 1] = v.y; h[q * 4 + 2] = v.z; h[q * 4 + 3] = v.w; }
    };
    uint32_t ha[72];
    typedef float (&A28)[28];
    float (&aq)[28] = (A28)acc1;
    {
      uint32_t gl[16];
      float (&u0)[32] = acc0, (&g0)[32] = acc1, (&g1)[32] = acc0, (&u1)[32] = acc1, (&g2)[32] = acc0, (&u2)[32] = acc1, (&gu)[32] = acc0;
      float (&ak)[28] = (A28)acc0, (&av)[28] = (A28)acc1, (&kv)[28] = (A28)acc1;
      {
        auto stag = [&](int i) { if (i == STAG && lead) asm volatile("bar.arrive 5, 256;" ::: "memory"); };
        auto sq6 = [&](int i) {
          if (G6 && i == SQ_AT) {
#pragma unroll
            for (int j = 0; j < 2; j++) {
              const uint32_t* f = &xf[96 + j];
              uint32_t q = hmul2(f[0], f[0]);
#pragma unroll
              for (int k = 1; k < 8; k++) q = hfma2(f[k * 2], f[k * 2], q);
              float v = bf_lo(q) + bf_hi(q);
              v += __shfl_xor_sync(~0u, v, 1);
              st[2 * j + 1] += v + __shfl_xor_sync(~0u, v, 2);
            }
            fence_regs(st);
          }
        };
        bar_sync(3 + wg, 128);
        WG_WAIT(1); release<6>(C);
        fence_regs(u0);
        park_raw(u0, XO_PARK);
#pragma unroll
        for (int j = 0; j < 2; j++) { st[2 * j] *= -1.0f / 448.0f; nm[j] = pack2(st[2 * j], st[2 * j]); }
        center(0, 28);
        if (STAG >= 0 && !lead) bar_sync(5, 256);
        grp<8>(ak, xf, dB + r, C);
        stag(0);
        center(28, 28);
        sq6(0);
        WG_WAIT(1); release<7>(C);
        fence_regs(g0);
        grp<9>(ak, xf, dB + r, C);
        stag(1);
        center(56, 28);
        sq6(1);
        WG_WAIT(1); release<8>(C);
        grp<10>(ak, xf, dB + r, C);
        stag(2);
        sq6(2);
        center(84, 28);
        WG_WAIT(1); release<9>(C);
        grp<11>(ak, xf, dB + r, C);
        stag(3);
        park_raw(g0, XO_G0);
#pragma unroll
        for (int j = 0; j < 2; j++)
          asm("rsqrt.approx.ftz.f32 %0, %1;" : "=f"(rstd[j]) : "f"(fmaxf(fmaf(st[2 * j + 1], 1.0f / 448.0f, -st[2 * j] * st[2 * j]), 0.f) + 1e-5f));
        fence_regs(rstd);
        WG_WAIT(1); release<10>(C);
      }
      auto glu0 = [&](int q) {
        if (q == 0) mbar_wait(bar + B_CS * 8, 0);
        const uint4 c = lds128(bar + (OFF_CS - OFF_BAR) + q * 64 + t * 16), g = lds128(park + XO_G0 + q * 2048);
        float y[32];
        uint32_t w[4];
#pragma unroll
        for (int e = 0; e < 4; e++) { const uint32_t v = hfma2(nm[e & 1], (&c.x)[e >> 1], (&g.x)[e]); y[e * 2] = bf_lo(v); y[e * 2 + 1] = bf_hi(v); }
        gelu_part(y, w, 0, 4);
        const uint4 u = lds128(park + q * 2048);
#pragma unroll
        for (int e = 0; e < 4; e++) w[e] = hmul2(w[e], hfma2(nm[e & 1], (&c.x)[2 + (e >> 1)], (&u.x)[e]));
        asm volatile("st.shared.v4.u32 [%0], {%1,%2,%3,%4};" ::"r"(park + q * 2048), "r"(w[0]), "r"(w[1]), "r"(w[2]), "r"(w[3]) : "memory");
      };
      auto gs = [&](int i) { if (i == GA) glu0(0); if (i == GB) glu0(1); if (i == GC) glu0(2); if (i == GD) glu0(3); };
      auto phi_k = [&](int q0, int q1) {
        const float rl[2] = {rstd[0] * 1.4426950409f, rstd[1] * 1.4426950409f};
#pragma unroll
        for (int q = q0; q < q1; q++) {
          uint32_t pk[4];
#pragma unroll
          for (int e = 0; e < 4; e++) {
            const int j = q * 4 + e;
            pk[e] = j < 14 ? pack2(phi(ak[j * 2], rstd[e & 1], rl[e & 1]), phi(ak[j * 2 + 1], rstd[e & 1], rl[e & 1])) : 0u;
          }
          stsm4((frag ^ (q << 5)) + XO_STG, pk[0], pk[1], pk[2], pk[3]);
        }
      };
      pass<12>(av, ak, xf, dB + r, C, nop, [&] { phi_k(0, 1); }, [&] { phi_k(1, 2); }, [&] { phi_k(2, 4); });
      {
        grp<16>(g1, xf, dB, C);
        WG_WAIT(1); release<15>(C);
        fence_regs(av);
        grp<17>(g1, xf, dB, C);
#pragma unroll
        for (int q = 0; q < 4; q++) {
          uint32_t vv[4];
#pragma unroll
          for (int e = 0; e < 4; e++) {
            const int j = q * 4 + e;
            vv[e] = j < 14 ? pack2(av[j * 2] * rstd[e & 1], av[j * 2 + 1] * rstd[e & 1]) : (t == 0 ? 0x3F803F80u : 0u);
          }
          stsm4((frag ^ (q << 5)) + XO_STG + 8192, vv[0], vv[1], vv[2], vv[3]);
        }
        WG_WAIT(1); release<16>(C);
        grp<18>(g1, xf, dB, C);
        FENCE_ASYNC_SMEM;
        bar_sync(3 + wg, 128);
        const uint32_t dk = (SB0 + wg * XW_BYTES + XO_STG) >> 4;
        WG_FENCE;
#pragma unroll
        for (int k = 0; k < 4; k++) wgmma_ss_n56_ta1tb1(kv, desc_lo(dk + 512 + k * 128), desc_lo(dk + k * 128), k);
        WG_COMMIT;
        WG_WAIT(2); release<17>(C);
        grp<19>(g1, xf, dB, C);
        WG_WAIT(1); release<18>(C);
        fence_regs(kv);
#pragma unroll
        for (int hh = 0; hh < 2; hh++) {
          const int v = warp * 16 + (lane >> 2) + hh * 8;
          const bool h1 = v < 56 ? v >= 28 : (v & 1);
          const int n = v < 56 ? (h1 ? v - 28 : v) : 28 + ((v - 56) >> 1);
          const uint32_t rowp = xw + XO_KV + (h1 ? 4096 : 0) + n * 128 + ((n & 7) << 4) + t * 4;
#pragma unroll
          for (int j = 0; j < 8; j++) {
            float a = h1 ? kv[((j >> 1) + 3) * 4 + hh * 2 + (j & 1)] : kv[(j >> 1) * 4 + hh * 2 + (j & 1)];
            if (j < 2 && h1 && t < 2) a = 0.f;
            if (j >= 6 && !h1 && t >= 2) a = 0.f;
            asm volatile("st.shared.f32 [%0], %1;" ::"r"(rowp ^ (j << 4)), "f"(a) : "memory");
          }
        }
        __syncwarp();
        if (lane == 0) mbar_arrive(bar + (B_KV + (lead ? 0 : 1)) * 8);
      }
      pass<20>(u1, g1, xf, dB, C, nop, [&] { gelu_part(g1, gl, 0, 6); }, [&] { gelu_part(g1, gl, 6, 12); }, [&] { gelu_part(g1, gl, 12, 16); });
      pass<24>(g2, u1, xf, dB, C, [&] { gs(24); }, [&] { mul_up(u1, gl); park_h(gl, 4); gs(25); }, [&] { gs(26); }, [&] { gs(27); });
      pass<28>(u2, g2, xf, dB, C, [&] { gs(28); }, [&] { gelu_part(g2, ha, 0, 6); }, [&] { gelu_part(g2, ha, 6, 12); }, [&] { gelu_part(g2, ha, 12, 16); gs(31); });
      pass<32, true>(gu, u2, xf, dB | (448u << 16), C, [&] { gs(32); }, [&] { mul_up(u2, ha); keep<16>(ha); gs(33); }, [&] { gs(34); }, [&] { gs(35); });
      pass<36>(aq, gu, xf, dB + r, C, [&] { gs(36); }, [&] {
        gelu_part(gu, ha + 16, 0, 8);
#pragma unroll
        for (int j = 0; j < 8; j++) ha[16 + j] = hmul2(ha[16 + j], pack2(gu[16 + j * 2], gu[16 + j * 2 + 1]));
        keep<8>(ha + 16);
      }, [&] { gs(38); if (GD == 38) unpark_h(ha + 40, 4); else unpark_h(ha + 24, 0); }, [&] { if (GD == 38) unpark_h(ha + 24, 0); else unpark_h(ha + 40, 4); });
    }
    TLREC(wg, 8);
    {
      G2State S;
      S.o2 = r * 256u;
      asm volatile("mapa.shared::cluster.u32 %0, %1, %2;" : "=r"(S.land) : "r"(sb + r * XW_BYTES + (tid & 127) * 16), "r"(r ^ 1));
      asm volatile("mapa.shared::cluster.u32 %0, %1, %2;" : "=r"(S.rbar) : "r"(bar + B_LAND * 8), "r"(r ^ 1));
      if (!lead) S.land = sb + (r ^ 1) * XW_BYTES + (tid & 127) * 16;
      S.stg = frag; S.lead = lead;
      g2_issue<I_G2, 0>(acc0, ha, C, S);
      g2_done<I_G2 - 1>(C);
      fence_regs(aq);
      const uint32_t okk = mbar_probe(bar + B_KVD * 8, 0);
      g2_issue<I_G2 + 1, 1>(acc0, ha, C, S);
      float pq[28];
      {
        const float rl[2] = {rstd[0] * 1.4426950409f, rstd[1] * 1.4426950409f};
#pragma unroll
        for (int j = 0; j < 28; j++) pq[j] = phi(aq[j], rstd[(j >> 1) & 1], rl[(j >> 1) & 1]);
      }
      fence_regs(pq);
      g2_done<I_G2>(C);
      mbar_ensure(okk, bar + B_KVD * 8, 0);
      float n0[16], n1[16];
      const uint32_t dk = (SB0 + r * XW_BYTES + XO_KVD) >> 4;
      WG_FENCE;
#pragma unroll
      for (int k = 0; k < 4; k++) {
        wgmma_tf32_n32(n0, pq[k * 4], pq[k * 4 + 2], pq[k * 4 + 1], pq[k * 4 + 3], desc_lo(dk + k * 2), k);
        wgmma_tf32_n32(n1, pq[k * 4 + 12], pq[k * 4 + 14], pq[k * 4 + 13], pq[k * 4 + 15], desc_lo(dk + 256 + k * 2), k);
      }
      WG_COMMIT;
      g2_issue<I_G2 + 2, 0>(acc1, ha, C, S);
      keep<8>(ha + 48);
      if (lead) {
        if (lane == 0) asm volatile("mbarrier.arrive.shared::cluster.b64 _, [%0];" ::"r"(S.rbar + (B_PEER - B_LAND) * 8) : "memory");
      } else {
        bar_sync(3 + wg, 128);
      }
      g2_done<I_G2 + 1>(C);
      fence_regs(n0); fence_regs(n1);
#pragma unroll
      for (int hh = 0; hh < 2; hh++) {
        const float* n = hh ? n1 : n0;
        float inv[2];
#pragma unroll
        for (int j = 0; j < 2; j++) inv[j] = __fdividef(1.0f, __shfl_sync(~0u, n[12 + 2 * j], (lane & 28) | 2) + 1e-6f);
#pragma unroll
        for (int j = 0; j < 8; j++) {
          const uint32_t o = pack2(n[j * 2] * inv[j & 1], n[j * 2 + 1] * inv[j & 1]);
          ha[56 + hh * 8 + j] = (j >= 6 && t >= 2) ? 0u : o;
        }
      }
      TLREC(wg, 9);
      uint32_t v[16];
      g2_issue<I_G2 + 3, 2>(acc0, ha, C, S);
      g2_done<I_G2 + 2>(C);
      g2_issue<I_G2 + 4, 1>(acc1, ha, C, S);
      mbar_wait(bar + (lead ? B_PEER : B_LAND) * 8, 0);
      g2_fetch(v, C, S, 1, 0);
      g2_done<I_G2 + 3>(C);
      g2_step<0>(acc0, acc1, v, ha, C, S, &P.out);
      g2_step<1>(acc1, acc0, v, ha, C, S, &P.out);
      g2_step<2>(acc0, acc1, v, ha, C, S, &P.out);
      g2_step<3>(acc1, acc0, v, ha, C, S, &P.out);
      g2_step<4>(acc0, acc1, v, ha, C, S, &P.out);
      g2_step<5>(acc1, acc0, v, ha, C, S, &P.out);
      g2_step<6>(acc0, acc1, v, ha, C, S, &P.out);
    }
    TLREC(wg, 17); TLREG(wg, 63);
  }
}

typedef CUresult (*EncFn)(CUtensorMap*, CUtensorMapDataType, cuuint32_t, void*, const cuuint64_t*, const cuuint64_t*, const cuuint32_t*, const cuuint32_t*,
                          CUtensorMapInterleave, CUtensorMapSwizzle, CUtensorMapL2promotion, CUtensorMapFloatOOBfill);

void enc(EncFn f, CUtensorMap* tm, int rank, const void* base, const cuuint64_t* gd, const cuuint64_t* gs, const cuuint32_t* bd, bool sw64 = false) {
  cuuint32_t es[5] = {1, 1, 1, 1, 1};
  f(tm, CU_TENSOR_MAP_DATA_TYPE_BFLOAT16, rank, (void*)base, gd, gs, bd, es, CU_TENSOR_MAP_INTERLEAVE_NONE, sw64 ? CU_TENSOR_MAP_SWIZZLE_64B : CU_TENSOR_MAP_SWIZZLE_128B,
    CU_TENSOR_MAP_L2_PROMOTION_L2_128B, CU_TENSOR_MAP_FLOAT_OOB_FILL_NONE);
}
void enc2(EncFn f, CUtensorMap* tm, const void* base, int cols, int rows, int bc, int br) {
  cuuint64_t gd[2] = {(cuuint64_t)cols, (cuuint64_t)rows}, gs[1] = {(cuuint64_t)cols * 2};
  cuuint32_t bd[2] = {(cuuint32_t)bc, (cuuint32_t)br};
  enc(f, tm, 2, base, gd, gs, bd, bc == 32);
}

}

extern "C" void kernel_launch(void* const* d_in, const int* in_sizes, int n_in, void* d_out, int out_size) {
  static EncFn f = nullptr;
  if (!f) {
    cudaDriverEntryPointQueryResult qr;
    cudaGetDriverEntryPoint("cuTensorMapEncodeTiled", (void**)&f, cudaEnableDefault, &qr);
    cudaFuncSetAttribute(fused_kernel, cudaFuncAttributeMaxDynamicSharedMemorySize, SMEM_BYTES);
  }
  Params P;
  P.x = (const __nv_bfloat16*)d_in[0];
  P.out = (__nv_bfloat16*)d_out;
  P.wqkv = (const __nv_bfloat16*)d_in[1];
  P.wo = (const __nv_bfloat16*)d_in[2];
  P.wg = (const __nv_bfloat16*)d_in[4];
  P.wu = (const __nv_bfloat16*)d_in[5];
  P.wd = (const __nv_bfloat16*)d_in[6];
  enc2(f, &P.tmX, P.x, 448, 2048, 64, 64);
  enc2(f, &P.tmU64, P.wu, 1792, 448, 64, 64);
  enc2(f, &P.tmG64, P.wg, 1792, 448, 64, 64);
  enc2(f, &P.tmG, P.wg, 1792, 448, 64, 112);
  enc2(f, &P.tmU, P.wu, 1792, 448, 64, 112);
  enc2(f, &P.tmQ, P.wqkv, 1344, 448, 64, 112);
  enc2(f, &P.tmG32, P.wg, 1792, 448, 32, 112);
  enc2(f, &P.tmU32, P.wu, 1792, 448, 32, 112);
  enc2(f, &P.tmWd96, P.wd, 448, 1792, 64, 96);
  enc2(f, &P.tmWd32, P.wd, 448, 1792, 64, 32);
  { cuuint64_t gd[3] = {448, 28, 16}, gs[2] = {896, 28 * 896}; cuuint32_t bd[3] = {64, 32, 2}; enc(f, &P.tmWo, 3, P.wo, gd, gs, bd); }
  enc2(f, &P.tmOut, d_out, 448, 2048, 64, 64);
  fused_kernel<<<128, 384, SMEM_BYTES, cudaStreamPerThread>>>(P);
}
```
